```python
import torch

def _softmax(x, axis=-1):
    return torch.softmax(x, dim=axis)
def _gelu(x):
    return torch.nn.functional.gelu(x, approximate="tanh")
def _silu(x):
    return torch.nn.functional.silu(x)
def _sigmoid(x):
    return torch.sigmoid(x)
def _layernorm(x, axis=-1, eps=1e-5):
    m = x.mean(dim=axis, keepdim=True)
    v = x.var(dim=axis, keepdim=True, unbiased=False)
    return (x - m) / torch.sqrt(v + eps)
def _scatter_add(tgt, idx, src, axis=0):
    return tgt.clone().index_add_(axis, idx, src)
def _segment_sum(src, seg, n):
    out = torch.zeros((n,) + src.shape[1:], dtype=src.dtype)
    return out.index_add_(0, seg, src)
def _pad(x, pw):
    flat = tuple(v for pair in reversed(pw) for v in pair)
    return torch.nn.functional.pad(x, flat)

kernel_name = 'standalone__deep_cross_xdeepfm__recsys'

def setup_inputs():

    _w = (lambda a: (lambda t: t.to(torch.bfloat16) if t.is_floating_point() else t)(torch.as_tensor(a)))
    B, F, D, L = 4096, 26, 16, 3
    V = min(1000000, 100000)
    Din = F * D
    return {
        "idx": _w((lambda lo, hi, *s: torch.randint(lo, hi, s))(0, V, B, F).to(torch.int64)),
        "table": _w((lambda *s: torch.randn(*s, dtype=torch.bfloat16) * 0.8)(V, D)),
        "ws_cin": _w((lambda *s: torch.randn(*s, dtype=torch.bfloat16) * 0.2)(L, F, F, F) * (1.0 / F)),
        "w_cin_out": _w((lambda *s: torch.randn(*s, dtype=torch.bfloat16) * 0.2)(L * F) * ((L * F) ** -0.5)),
        "w_dnn1": _w((lambda *s: torch.randn(*s, dtype=torch.bfloat16) * 0.8)(Din, Din) * (Din ** -0.5)),
        "b_dnn1": _w((lambda *s: torch.randn(*s, dtype=torch.bfloat16) * 3.2)(Din) * 0.1),
        "w_dnn2": _w((lambda *s: torch.randn(*s, dtype=torch.bfloat16) * 0.2)(Din) * (Din ** -0.5)),
        "b_out": _w((lambda *s: torch.randn(*s, dtype=torch.bfloat16) * 0.4)(1)),
    }

def reference(idx, table, ws_cin, w_cin_out, w_dnn1, b_dnn1, w_dnn2, b_out):
    x0 = table[idx]
    B = x0.shape[0]
    L = ws_cin.shape[0]
    xk = x0
    pooled = []
    for l in range(L):
        xk = torch.einsum('bid,bjd,hij->bhd', xk, x0, ws_cin[l])
        pooled.append(xk.sum(axis=-1))
    p_plus = torch.stack(pooled, axis=1).reshape(B, -1)
    logit_cin = p_plus @ w_cin_out
    h = x0.reshape(B, -1)
    h = _gelu(h @ w_dnn1 + b_dnn1)
    logit_dnn = h @ w_dnn2
    return logit_cin + logit_dnn + b_out
```

```cpp
#include <cuda_runtime.h>
#include <cuda_bf16.h>
#include <cuda.h>
#include <stdint.h>

namespace {

constexpr int kThreads   = 512;
constexpr int kFoldCtas  = 4;
constexpr int kMainCtas  = 128;
constexpr int kF         = 26;
constexpr unsigned kPaceClks   = 130;
constexpr unsigned kLateW1Clks = 3600;
constexpr int kHandOver = 15;

constexpr int OFF_WA  = 0;
constexpr int W1_CHUNK = 49152;
constexpr int OFF_WD  = 3 * W1_CHUNK;
constexpr int OFF_CW  = OFF_WA;
constexpr int CW_LIN  = 2048;
constexpr int CW_C1 = 6, CW_C2 = 14;
constexpr int CW_GB0 = CW_C1 * 256, CW_GB1 = (CW_C2 - CW_C1) * 256, CW_GB2 = (22 - CW_C2) * 256;
constexpr int CW_P0 = CW_LIN, CW_P1 = CW_P0 + 7 * CW_GB0, CW_P2 = CW_P1 + 7 * CW_GB1;
constexpr int CW_BYTES = CW_P2 + 7 * CW_GB2;
constexpr int OFF_W1R = OFF_WD + 12288;
constexpr int WR_BYTES = 14 * 1024;
constexpr int OFF_X   = OFF_W1R + WR_BYTES;
constexpr int XF      = 2080;
constexpr int OFF_BW  = OFF_X + kF * XF;
constexpr int OFF_DP  = OFF_BW + 26 * 4 * 16;
constexpr int OFF_LD  = OFF_DP + 256;
constexpr int OFF_BAR = OFF_LD + 448;
constexpr int SMEM_USED = OFF_BAR + 256;
constexpr int SMEM_ALLOC = SMEM_USED + 1024;

__device__ const unsigned char kSlotLin[32] = {0,1,4,13,9,8,14,21,12,10,18,6,15,11,7,3,22,20,19,23,24,25,2,5,16,17,255,255,255,255,255,255};
__device__ __align__(16) const unsigned short kLdsmOff[7*32] = {0,2080,8320,27040,18720,16640,29120,43680,16,2096,8336,27056,18736,16656,29136,43696,24960,20800,37440,12480,31200,22880,14560,6240,24976,20816,37456,12496,31216,22896,14576,6256,45760,41600,39520,47840,49920,52000,4160,10400,45776,41616,39536,47856,49936,52016,4176,10416,33280,35360,29120,43680,6240,14560,20800,24960,33296,35376,29136,43696,6256,14576,20816,24976,10400,4160,14560,6240,10400,4160,16640,18720,10416,4176,14576,6256,10416,4176,16656,18736,6240,14560,2080,0,0,2080,37440,12480,6256,14576,2096,16,16,2096,37456,12496,27040,8320,16640,18720,12480,37440,22880,31200,27056,8336,16656,18736,12496,37456,22896,31216,18720,16640,20800,24960,43680,29120,39520,47840,18736,16656,20816,24976,43696,29136,39536,47856,12480,37440,35360,33280,47840,39520,8320,27040,12496,37456,35376,33296,47856,39536,8336,27056,43680,29120,52000,49920,27040,8320,35360,33280,43696,29136,52016,49936,27056,8336,35376,33296,49920,52000,22880,31200,24960,20800,52000,49920,49936,52016,22896,31216,24976,20816,52016,49936,31200,22880,41600,45760,33280,35360,41600,45760,31216,22896,41616,45776,33296,35376,41616,45776,47840,39520,4160,10400,45760,41600,2080,0,47856,39536,4176,10416,45776,41616,2096,16,47840,39520,4160,10400,45760,41600,2080,0,47856,39536,4176,10416,45776,41616,2096,16};
#define PROD_LIST X(0,0,0,1) X(1,0,0,3) X(2,0,0,4) X(3,0,1,2) X(4,0,1,4) X(5,0,1,5) X(6,0,2,3) X(7,0,2,5) X(8,0,2,6) X(9,0,3,4) X(10,0,3,6) X(11,0,3,7) X(12,0,4,5) X(13,0,4,7) X(14,0,4,8) X(15,0,5,6) X(16,0,5,8) X(17,0,5,9) X(18,0,6,7) X(19,0,6,9) X(20,0,6,10) X(21,0,7,8) X(22,0,7,10) X(23,0,7,11) X(24,0,8,9) X(25,0,8,11) X(26,0,8,12) X(27,0,9,10) X(28,0,9,12) X(29,0,9,0) X(30,0,10,11) X(31,0,10,0) X(32,0,10,1) X(33,0,11,12) X(34,0,11,1) X(35,0,11,2) X(36,0,12,0) X(37,0,12,2) X(38,0,12,3) X(39,1,2,2) X(40,1,5,5) X(41,1,11,11) X(42,2,3,12) X(43,3,7,8)
constexpr int kMixQ = 0;
constexpr int kLin0 = 2, kLin1 = 5, kLin2 = 11, kLin3 = 7;
#define LDSM_LIST L(0,2,5) L(1,11,7) L(2,0,1) L(3,3,4) L(4,6,8) L(5,9,10)
#define LDSM_LAST 12
__device__ __align__(16) const uint32_t kSlotTab[352] = {0x3f821453,0x3f814037,0x3f82dc21,0x3f813c1d,0x3f820805,0x3f80d002,0x3f8770e2,0x3f8774fc,0x3f855c8f,0x3f855041,0x3f835cbe,0x3f834c56,0x3f828488,0x3f82783a,0x3f8498db,0x3f849cf5,0x3f83bc8b,0x3f83b03d,0x3f842cc0,0x3f841c58,0x3f889c97,0x3f889049,0x3f87d8e3,0x3f87dcfd,0x3f813803,0x3f82d807,0x3f81a41e,0x3f81a004,0x3f83a809,0x3f83ac23,0x3f87897e,0x3f85c8aa,0x3f83b457,0x3f83c4bf,0x3f841424,0x3f84100a,0x3f888815,0x3f888c2f,0x3f8801e7,0x3f87d0af,0x3f84ec5a,0x3f84fcc2,0x3f87542c,0x3f875012,0x3f86180f,0x3f861c29,0x3f876cc8,0x3f82f0a3,0x3f85480d,0x3f854c27,0x3f835070,0x3f8568dd,0x3f83c0a5,0x3f8358a4,0x3f85dd2c,0x3f88b533,0x3f84e00c,0x3f84e426,0x3f87607a,0x3f878564,0x3f863cf9,0x3f8638df,0x3f85ccc4,0x3f88a4cb,0x3f827006,0x3f827420,0x3f86f879,0x3f871d63,0x3f897d01,0x3f8978e7,0x3f85c076,0x3f88987d,0x3f856cf7,0x3f83b871,0x3f8430da,0x3f8434f4,0x3f88a0b1,0x3f88d1e9,0x3f87e531,0x3f87f599,0x3f8560a9,0x3f82806e,0x3f8708e1,0x3f870cfb,0x3f8970b3,0x3f89a1eb,0x3f848873,0x3f862877,0x3f86b562,0x3f869078,0x3f85d0de,0x3f85d4f8,0x3f827c54,0x3f875c60,0x3f84a10f,0x3f864113,0x3f8504f6,0x3f8500dc,0x3f877916,0x3f87814a,0x3f88c59b,0x3f86517b,0x3f87d4c9,0x3f8974cd,0x3f86a4fa,0x3f86a0e0,0x3f85d912,0x3f85e146,0x3f889463,0x3f85bc5c,0x3f87e117,0x3f89811b,0x3f88acff,0x3f88a8e5,0x3f8a511d,0x3f8a5951,0x3f88bd67,0x3f85e560,0x3f87fdcd,0x3f899dd1,0x3f84f8a8,0x3f8428a6,0x3f8795cc,0x3f8700ad,0x3f89959d,0x3f898535,0x3f82e86f,0x3f81ac52,0x3f88b94d,0x3f88b119,0x3f8a71ed,0x3f8a40b5,0x3f864d61,0x3f85752b,0x3f8704c7,0x3f86f45f,0x3f89f150,0x3f89e91c,0x3f877d30,0x3f8490a7,0x3f864947,0x3f850d2a,0x3f8a44cf,0x3f8a3467,0x3f8698ac,0x3f8791b2,0x3f87217d,0x3f86b97c,0x3f896465,0x3f87c461,0x3f842072,0x3f857111,0x3f89d8b4,0x3f8a09ec,0x3f87152f,0x3f86ad2e,0x3f89894f,0x3f87e94b,0x3f8a3881,0x3f8a5d6b,0x3f8630ab,0x3f878d98,0x3f8865ce,0x3f8861b4,0x3f8999b7,0x3f87f9b3,0x3f88307c,0x3f885566,0x3f88c9b5,0x3f88cdcf,0x3f8a6185,0x3f8a7e3b,0x3f85545b,0x3f8564c3,0x3f871115,0x3f871949,0x3f86bd96,0x3f872597,0x3f885980,0x3f88da1d,0x3f868c5e,0x3f869cc6,0x3f884918,0x3f88514c,0x3f8931b6,0x3f8935d0,0x3f87f17f,0x3f88d603,0x3f89cc66,0x3f89dcce,0x3f84183e,0x3f84e840,0x3f8a163a,0x3f89f984,0x3f8a5537,0x3f89ed36,0x3f857945,0x3f84f074,0x3f8a6dd3,0x3f8a69b9,0x3f894638,0x3f892982,0x3f8a7607,0x3f8a0e06,0x3f89f56a,0x3f89d080,0x3f86f045,0x3f868844,0x3f89ae39,0x3f899183,0x3f8a304d,0x3f89c84c,0x3f892568,0x3f89007e,0x3f86ec2b,0x3f86842a,0x3f89fd9e,0x3f8a659f,0x3f884d32,0x3f885d9a,0x3f86b148,0x3f86a914,0x3f8a7a21,0x3f8a1220,0x3f8a1e6e,0x3f8a866f,0x3f84803f,0x3f862043,0x3f89214e,0x3f89191a,0x3f8a2c33,0x3f89c432,0x3f89d49a,0x3f8a3c9b,0x3f8494c1,0x3f8634c5,0x3f84f48e,0x3f84248c,0x3f8a48e9,0x3f89e0e8,0x3f892d9c,0x3f891d34,0x3f886e02,0x3f893e04,0x3f8a01b8,0x3f8a05d2,0x3f882848,0x3f88f84a,0x3f862c91,0x3f848c8d,0x3f883cca,0x3f890ccc,0x3f869492,0x3f86fc93,0x3f8840e4,0x3f8910e6,0x3f86245d,0x3f848459,0x3f88242e,0x3f88f430,0x3f868010,0x3f86e811,0x3f8869e8,0x3f8939ea,0x3f89b253,0x3f89aa1f,0x3f87c047,0x3f89604b,0x3f8a1a54,0x3f8a8255,0x3f80d41c,0x3f820c1f,0x3f88fc64,0x3f882c62,0x3f87bc2d,0x3f895c31,0x3f89c018,0x3f8a2819,0x3f875846,0x3f876494,0x3f88f016,0x3f882014,0x3f87c87b,0x3f89687f,0x3f89e502,0x3f8a4d03,0x3f85b842,0x3f85c490,0x3f896c99,0x3f87cc95,0x3f82e03b,0x3f82ec89,0x3f890498,0x3f883496,0x3f834422,0x3f834008,0x3f895817,0x3f87b813,0x3f81a838,0x3f82186d,0x3f891500,0x3f8844fe,0x3f85b428,0x3f85b00e,0x3f898d69,0x3f87ed65,0x3f83483c,0x3f83548a,0x3f8908b2,0x3f8838b0,0x3f847c25,0x3f84780b,0x3f000000,0x3f006c1b,0x3f01b06c,0x3f057d5f,0x3f03ccf3,0x3f0360d8,0x3f05e97a,0x3f08de37,0x3f051144,0x3f04390e,0x3f0799e6,0x3f0288a2,0x3f065595,0x3f04a529,0x3f02f4bd,0x3f014451,0x3f094a52,0x3f08721c,0x3f080601,0x3f09b66d,0x3f0a2288,0x3f0a8ea3,0x3f00d836,0x3f021c87,0x3f855875,0x3f89a605,0x3f83c8d9,0x3f821039,0x3f8768ae,0x3f89421e,0x3f86452d,0x3f806801,0x3f06c1b0,0x3f072dcb,0x3f88c181,0x3f8a8a89,0x3f82e455,0x00000000,0x3f850910,0x3f8729b1};


__device__ uint4 g_wimg[CW_BYTES / 16];
__device__ uint4 g_rimg[2 * WR_BYTES / 16];
constexpr int kFlagRep = 8;
__device__ unsigned int g_flag[2 * kFlagRep * 32];
__device__ unsigned int g_seen;
__device__ __forceinline__ unsigned clk32x() { unsigned t; asm volatile("mov.u32 %0, %%clock;" : "=r"(t)); return t; }

__device__ __forceinline__ void wgmma_n56_rs(float (&d)[28], uint32_t a0, uint32_t a1, uint32_t a2, uint32_t a3, uint64_t descB, int scaleD) {
  asm volatile("{\n.reg .pred p;\nsetp.ne.b32 p, %33, 0;\n"
    "wgmma.mma_async.sync.aligned.m64n56k16.f32.bf16.bf16 {%0, %1, %2, %3, %4, %5, %6, %7, %8, %9, %10, %11, %12, %13, %14, %15, %16, %17, %18, %19, %20, %21, %22, %23, %24, %25, %26, %27}, {%28, %29, %30, %31}, %32, p, 1, 1, 0;\n}\n"
    : "+f"(d[0]), "+f"(d[1]), "+f"(d[2]), "+f"(d[3]), "+f"(d[4]), "+f"(d[5]), "+f"(d[6]), "+f"(d[7]), "+f"(d[8]), "+f"(d[9]), "+f"(d[10]), "+f"(d[11]), "+f"(d[12]), "+f"(d[13]), "+f"(d[14]), "+f"(d[15]), "+f"(d[16]), "+f"(d[17]), "+f"(d[18]), "+f"(d[19]), "+f"(d[20]), "+f"(d[21]), "+f"(d[22]), "+f"(d[23]), "+f"(d[24]), "+f"(d[25]), "+f"(d[26]), "+f"(d[27])
    : "r"(a0), "r"(a1), "r"(a2), "r"(a3), "l"(descB), "r"(scaleD));
}
__device__ __forceinline__ void wgmma_n32_rs(float (&d)[16], uint32_t a0, uint32_t a1, uint32_t a2, uint32_t a3, uint64_t descB, int scaleD) {
  asm volatile("{\n.reg .pred p;\nsetp.ne.b32 p, %21, 0;\n"
    "wgmma.mma_async.sync.aligned.m64n32k16.f32.bf16.bf16 {%0, %1, %2, %3, %4, %5, %6, %7, %8, %9, %10, %11, %12, %13, %14, %15}, {%16, %17, %18, %19}, %20, p, 1, 1, 0;\n}\n"
    : "+f"(d[0]), "+f"(d[1]), "+f"(d[2]), "+f"(d[3]), "+f"(d[4]), "+f"(d[5]), "+f"(d[6]), "+f"(d[7]), "+f"(d[8]), "+f"(d[9]), "+f"(d[10]), "+f"(d[11]), "+f"(d[12]), "+f"(d[13]), "+f"(d[14]), "+f"(d[15])
    : "r"(a0), "r"(a1), "r"(a2), "r"(a3), "l"(descB), "r"(scaleD));
}
__device__ __forceinline__ void wgmma_n192_ss(float (&d)[96], uint64_t descA, uint64_t descB, int scaleD) {
  asm volatile("{\n.reg .pred p;\nsetp.ne.b32 p, %98, 0;\n"
    "wgmma.mma_async.sync.aligned.m64n192k16.f32.bf16.bf16 {%0, %1, %2, %3, %4, %5, %6, %7, %8, %9, %10, %11, %12, %13, %14, %15, %16, %17, %18, %19, %20, %21, %22, %23, %24, %25, %26, %27, %28, %29, %30, %31, %32, %33, %34, %35, %36, %37, %38, %39, %40, %41, %42, %43, %44, %45, %46, %47, %48, %49, %50, %51, %52, %53, %54, %55, %56, %57, %58, %59, %60, %61, %62, %63, %64, %65, %66, %67, %68, %69, %70, %71, %72, %73, %74, %75, %76, %77, %78, %79, %80, %81, %82, %83, %84, %85, %86, %87, %88, %89, %90, %91, %92, %93, %94, %95}, %96, %97, p, 1, 1, 0, 1;\n}\n"
    : "+f"(d[0]), "+f"(d[1]), "+f"(d[2]), "+f"(d[3]), "+f"(d[4]), "+f"(d[5]), "+f"(d[6]), "+f"(d[7]), "+f"(d[8]), "+f"(d[9]), "+f"(d[10]), "+f"(d[11]), "+f"(d[12]), "+f"(d[13]), "+f"(d[14]), "+f"(d[15]), "+f"(d[16]), "+f"(d[17]), "+f"(d[18]), "+f"(d[19]), "+f"(d[20]), "+f"(d[21]), "+f"(d[22]), "+f"(d[23]), "+f"(d[24]), "+f"(d[25]), "+f"(d[26]), "+f"(d[27]), "+f"(d[28]), "+f"(d[29]), "+f"(d[30]), "+f"(d[31]), "+f"(d[32]), "+f"(d[33]), "+f"(d[34]), "+f"(d[35]), "+f"(d[36]), "+f"(d[37]), "+f"(d[38]), "+f"(d[39]), "+f"(d[40]), "+f"(d[41]), "+f"(d[42]), "+f"(d[43]), "+f"(d[44]), "+f"(d[45]), "+f"(d[46]), "+f"(d[47]), "+f"(d[48]), "+f"(d[49]), "+f"(d[50]), "+f"(d[51]), "+f"(d[52]), "+f"(d[53]), "+f"(d[54]), "+f"(d[55]), "+f"(d[56]), "+f"(d[57]), "+f"(d[58]), "+f"(d[59]), "+f"(d[60]), "+f"(d[61]), "+f"(d[62]), "+f"(d[63]), "+f"(d[64]), "+f"(d[65]), "+f"(d[66]), "+f"(d[67]), "+f"(d[68]), "+f"(d[69]), "+f"(d[70]), "+f"(d[71]), "+f"(d[72]), "+f"(d[73]), "+f"(d[74]), "+f"(d[75]), "+f"(d[76]), "+f"(d[77]), "+f"(d[78]), "+f"(d[79]), "+f"(d[80]), "+f"(d[81]), "+f"(d[82]), "+f"(d[83]), "+f"(d[84]), "+f"(d[85]), "+f"(d[86]), "+f"(d[87]), "+f"(d[88]), "+f"(d[89]), "+f"(d[90]), "+f"(d[91]), "+f"(d[92]), "+f"(d[93]), "+f"(d[94]), "+f"(d[95])
    : "l"(descA), "l"(descB), "r"(scaleD));
}
__device__ __forceinline__ void wgmma_n16_ss(float (&d)[8], uint64_t descA, uint64_t descB, int scaleD) {
  asm volatile("{\n.reg .pred p;\nsetp.ne.b32 p, %10, 0;\n"
    "wgmma.mma_async.sync.aligned.m64n16k16.f32.bf16.bf16 {%0, %1, %2, %3, %4, %5, %6, %7}, %8, %9, p, 1, 1, 0, 1;\n}\n"
    : "+f"(d[0]), "+f"(d[1]), "+f"(d[2]), "+f"(d[3]), "+f"(d[4]), "+f"(d[5]), "+f"(d[6]), "+f"(d[7])
    : "l"(descA), "l"(descB), "r"(scaleD));
}


__device__ __forceinline__ uint32_t smem_u32(const void* p) { return (uint32_t)__cvta_generic_to_shared(p); }
__device__ __forceinline__ uint64_t mk64(uint32_t lo, uint32_t hi) { return ((uint64_t)hi << 32) | lo; }
__device__ __forceinline__ void wg_fence() { asm volatile("wgmma.fence.sync.aligned;" ::: "memory"); }
__device__ __forceinline__ void wg_commit() { asm volatile("wgmma.commit_group.sync.aligned;" ::: "memory"); }
template <int N> __device__ __forceinline__ void wg_wait() { asm volatile("wgmma.wait_group.sync.aligned %0;" ::"n"(N) : "memory"); }
__device__ __forceinline__ void mbar_init(uint32_t bar, uint32_t cnt) { asm volatile("mbarrier.init.shared::cta.b64 [%0], %1;" ::"r"(bar), "r"(cnt) : "memory"); }
__device__ __forceinline__ void mbar_arrive(uint32_t bar) { asm volatile("mbarrier.arrive.shared::cta.b64 _, [%0];" ::"r"(bar) : "memory"); }
__device__ __forceinline__ void mbar_expect_tx(uint32_t bar, uint32_t bytes) { asm volatile("mbarrier.arrive.expect_tx.shared::cta.b64 _, [%0], %1;" ::"r"(bar), "r"(bytes) : "memory"); }
__device__ __forceinline__ void mbar_wait(uint32_t bar, uint32_t parity) {
  asm volatile("{\n.reg .pred p;\n.reg .u32 c;\nmov.u32 c, 0;\n"
               "WL_%=:\nmbarrier.try_wait.parity.shared::cta.b64 p, [%0], %1;\n@p bra WD_%=;\n"
               "add.u32 c, c, 1;\nsetp.lt.u32 p, c, 4194304;\n@p bra WL_%=;\ntrap;\nWD_%=:\n}" ::"r"(bar), "r"(parity) : "memory");
}
__device__ __forceinline__ void mbar_wait_cluster(uint32_t bar, uint32_t parity) {
  asm volatile("{\n.reg .pred p;\n.reg .u32 c;\nmov.u32 c, 0;\n"
               "WL_%=:\nmbarrier.try_wait.parity.acquire.cluster.shared::cta.b64 p, [%0], %1;\n@p bra WD_%=;\n"
               "add.u32 c, c, 1;\nsetp.lt.u32 p, c, 4194304;\n@p bra WL_%=;\ntrap;\nWD_%=:\n}" ::"r"(bar), "r"(parity) : "memory");
}
__device__ __forceinline__ void mbar_arrive_if(uint32_t bar, bool pred) {
  asm volatile("{\n.reg .pred p;\nsetp.ne.u32 p, %1, 0;\n@p mbarrier.arrive.shared::cta.b64 _, [%0];\n}" ::"r"(bar), "r"((uint32_t)pred) : "memory");
}
__device__ __forceinline__ void fence_async_smem() { asm volatile("fence.proxy.async.shared::cta;" ::: "memory"); }
__device__ __forceinline__ void named_bar(int id, int n) { asm volatile("bar.sync %0, %1;" ::"r"(id), "r"(n) : "memory"); }
__device__ __forceinline__ void mma_bf16(float (&d)[4], uint32_t a0, uint32_t a1, uint32_t a2, uint32_t a3, uint32_t b0, uint32_t b1) {
  asm volatile("mma.sync.aligned.m16n8k16.row.col.f32.bf16.bf16.f32 {%0,%1,%2,%3}, {%4,%5,%6,%7}, {%8,%9}, {%0,%1,%2,%3};"
               : "+f"(d[0]), "+f"(d[1]), "+f"(d[2]), "+f"(d[3]) : "r"(a0), "r"(a1), "r"(a2), "r"(a3), "r"(b0), "r"(b1));
}
__device__ __forceinline__ void bulk_g2s(uint32_t dst, const void* src, uint32_t bytes, uint32_t bar) {
  asm volatile("cp.async.bulk.shared::cluster.global.mbarrier::complete_tx::bytes [%0], [%1], %2, [%3];" ::"r"(dst), "l"(src), "r"(bytes), "r"(bar) : "memory");
}
__device__ __forceinline__ void tma3d(uint32_t dst, const CUtensorMap* m, int c0, int c1, int c2, uint32_t bar) {
  asm volatile("cp.async.bulk.tensor.3d.shared::cluster.global.mbarrier::complete_tx::bytes [%0], [%1, {%3,%4,%5}], [%2];" ::"r"(dst), "l"(m), "r"(bar), "r"(c0), "r"(c1), "r"(c2) : "memory");
}
__device__ __forceinline__ uint32_t mapa(uint32_t addr, uint32_t rank) { uint32_t r; asm("mapa.shared::cluster.u32 %0, %1, %2;" : "=r"(r) : "r"(addr), "r"(rank)); return r; }
__device__ __forceinline__ void st_async_f32(uint32_t addr, float v, uint32_t bar) {
  asm volatile("st.async.weak.shared::cluster.mbarrier::complete_tx::bytes.f32 [%0], %1, [%2];" ::"r"(addr), "f"(v), "r"(bar) : "memory");
}
__device__ __forceinline__ void cp_async16(uint32_t dst, const void* src) { asm volatile("cp.async.cg.shared.global [%0], [%1], 16;" ::"r"(dst), "l"(src) : "memory"); }
__device__ __forceinline__ void cp_commit() { asm volatile("cp.async.commit_group;" ::: "memory"); }
template <int N> __device__ __forceinline__ void cp_wait() { asm volatile("cp.async.wait_group %0;" ::"n"(N) : "memory"); }
__device__ __forceinline__ void bulk_s2peer(uint32_t dst, uint32_t src, uint32_t bytes, uint32_t bar) {
  asm volatile("cp.async.bulk.shared::cluster.shared::cta.mbarrier::complete_tx::bytes [%0], [%1], %2, [%3];" ::"r"(dst), "r"(src), "r"(bytes), "r"(bar) : "memory");
}
__device__ __forceinline__ void bulk_s2g(void* dst, uint32_t src, uint32_t bytes) {
  asm volatile("cp.async.bulk.global.shared::cta.bulk_group [%0], [%1], %2;" ::"l"(dst), "r"(src), "r"(bytes) : "memory");
}
__device__ __forceinline__ void ldsm_x4_t(uint32_t addr, uint32_t& r0, uint32_t& r1, uint32_t& r2, uint32_t& r3) {
  asm volatile("ldmatrix.sync.aligned.m8n8.x4.trans.shared.b16 {%0,%1,%2,%3}, [%4];" : "=r"(r0), "=r"(r1), "=r"(r2), "=r"(r3) : "r"(addr) : "memory");
}
__device__ __forceinline__ void ldsm_x2_t(uint32_t addr, uint32_t& r0, uint32_t& r1) {
  asm volatile("ldmatrix.sync.aligned.m8n8.x2.trans.shared.b16 {%0,%1}, [%2];" : "=r"(r0), "=r"(r1) : "r"(addr) : "memory");
}
__device__ __forceinline__ uint32_t bmul(uint32_t a, uint32_t b) {
  __nv_bfloat162 r = __hmul2(*reinterpret_cast<__nv_bfloat162*>(&a), *reinterpret_cast<__nv_bfloat162*>(&b));
  return *reinterpret_cast<uint32_t*>(&r);
}
__device__ __forceinline__ uint32_t bmul_lo(uint32_t a, uint32_t b) {
  __nv_bfloat162 r = __hmul2(*reinterpret_cast<__nv_bfloat162*>(&a), __low2bfloat162(*reinterpret_cast<__nv_bfloat162*>(&b)));
  return *reinterpret_cast<uint32_t*>(&r);
}
__device__ __forceinline__ float tanh_fast(float x) { float y; asm("tanh.approx.f32 %0, %1;" : "=f"(y) : "f"(x)); return y; }
__device__ __forceinline__ float bf2f(unsigned short v) { return __uint_as_float((uint32_t)v << 16); }
__device__ __forceinline__ uint32_t pack_bf16(float lo, float hi) { uint32_t r; asm("cvt.rn.bf16x2.f32 %0, %1, %2;" : "=r"(r) : "f"(hi), "f"(lo)); return r; }

__device__ __forceinline__ void forward_rounds(uint32_t sb, uint32_t rank, int r0, int step, uint32_t bar_l, uint32_t bar_r) {
  const int lane = threadIdx.x & 31;
  const uint32_t fsrc = sb + OFF_X + (2 * (lane & 1) + rank) * XF;
  const uint32_t fdst = mapa(fsrc, rank ^ 1), rbar = mapa(bar_r, rank ^ 1);
#pragma unroll 1
  for (int r = r0; r < 7; r += step) {
    mbar_wait(bar_l + 8 * r, 0);
    fence_async_smem();
    if (lane < (r < 6 ? 2 : 1)) bulk_s2peer(fdst + r * 4 * XF, fsrc + r * 4 * XF, 2048, rbar + 8 * r);
    __syncwarp();
  }
}

__device__ __forceinline__ void wait_flags(const unsigned int* p) {
  for (int it = 0; it < (1 << 21); it++) {
    uint32_t f;
    asm volatile("ld.relaxed.gpu.global.u32 %0, [%1];" : "=r"(f) : "l"(p) : "memory");
    if (f == 0x01010101u) return;
  }
  __trap();
}

__device__ __forceinline__ void fold_cta(uint8_t* smem, const __nv_bfloat16* __restrict__ ws, const __nv_bfloat16* __restrict__ cout,
                                         const __nv_bfloat16* __restrict__ w1) {
  const int tid = threadIdx.x, phi = blockIdx.x, lane = tid & 31, warp = tid >> 5;
  constexpr int WB = 17576 * 2;
  constexpr int W3A = 14 * 1352;
  const int i0 = 8 * phi;
  const int nI = phi < 3 ? 8 : 2;
  const int w1len = nI * 1352;
  const uint32_t* sW3 = reinterpret_cast<const uint32_t*>(smem);
  const uint8_t* sW2 = smem + 35200;
  const unsigned short* sW1 = reinterpret_cast<const unsigned short*>(smem + 70400);
  uint32_t* sWh = reinterpret_cast<uint32_t*>(smem + 81408);
  float* sT   = reinterpret_cast<float*>(smem + 86528);
  float* sA   = reinterpret_cast<float*>(smem + 108160);
  float* sC   = reinterpret_cast<float*>(smem + 108992);
  const uint4* sTab = reinterpret_cast<const uint4*>(smem + 109440);
  unsigned char* sLin = smem + 110848;
  constexpr int OFF_RS = 111104;
  constexpr int OFF_SG = 119296, OFF_SX = OFF_SG + 5632, OFF_SL = OFF_SX + 5632;
  const uint32_t sb = smem_u32(smem), bar = sb + 110912;
  if (warp == 14) {
    if (lane == 0) {
      mbar_init(bar, 1); mbar_init(bar + 8, 1); mbar_init(bar + 24, 1);
      asm volatile("fence.mbarrier_init.release.cluster;" ::: "memory");
      mbar_expect_tx(bar + 8, w1len + 352 * 4);
      bulk_g2s(sb + 70400, reinterpret_cast<const char*>(ws) + i0 * 1352, w1len, bar + 8);
      bulk_g2s(sb + 109440, kSlotTab, 352 * 4, bar + 8);
    }
    __syncwarp();
    asm volatile("bar.arrive 1, 480;" ::: "memory");
    if (lane == 0) {
      mbar_expect_tx(bar, W3A);            bulk_g2s(sb, ws + 2 * 17576, W3A, bar);
      mbar_expect_tx(bar + 24, WB - W3A);  bulk_g2s(sb + W3A, reinterpret_cast<const char*>(ws + 2 * 17576) + W3A, WB - W3A, bar + 24);
    }
    return;
  }
  if (warp == 15) {
    const int nrow = phi < 3 ? 128 : 32;
#pragma unroll 4
    for (int u = lane; u < nrow * 4; u += 32) {
      const int kl = u >> 2, kg = kl >> 3, r8 = kl & 7;
      const int atom = 2 * (kg >> 3) + (kg & 1), lc = 2 * ((kg & 7) >> 1) + (u & 1);
      cp_async16(sb + OFF_RS + ((u >> 1) & 1) * 4096 + atom * 1024 + r8 * 128 + ((lc ^ r8) << 4),
                 reinterpret_cast<const uint4*>(w1 + (128 * phi + kl) * 416 + 384) + (u & 3));
    }
    cp_commit();
    cp_wait<0>();
    fence_async_smem();
    __syncwarp();
    if (lane == 0) {
      const uint32_t bytes = phi < 3 ? 4096 : 2048;
#pragma unroll
      for (int r = 0; r < 2; r++) bulk_s2g(reinterpret_cast<uint8_t*>(g_rimg) + r * WR_BYTES + phi * 4096, sb + OFF_RS + r * 4096, bytes);
      asm volatile("cp.async.bulk.commit_group;" ::: "memory");
      asm volatile("cp.async.bulk.wait_group 0;" ::: "memory");
    }
    __syncwarp();
    if (lane < kFlagRep) asm volatile("st.relaxed.gpu.global.u8 [%0], %1;" ::"l"(reinterpret_cast<unsigned char*>(&g_flag[lane * 32]) + phi), "r"(1u) : "memory");
    return;
  }
  const unsigned short cv = tid < 78 ? __bfloat16_as_ushort(cout[tid]) : (unsigned short)0;
  const unsigned char lv = (tid >= 96 && tid < 128) ? kSlotLin[tid - 96] : (unsigned char)0;
  for (int i = tid; i < 26 * 27; i += 448) {
    const int h = i / 27, p = i - h * 27, st = h * 1352 + i0 * 52, a0 = st & ~15;
    if (a0 + p * 16 < st + nI * 52) cp_async16(sb + 35200 + h * 432 + p * 16, reinterpret_cast<const char*>(ws + 17576) + a0 + p * 16);
  }
  cp_commit();
  for (int i = tid; i < 640; i += 448) sWh[i] = 0;
  if (tid < 78) sC[tid] = bf2f(cv);
  if (tid >= 96 && tid < 128) sLin[tid - 96] = lv;
  asm volatile("bar.sync 1, 480;" ::: "memory");
  if (tid >= 26 && tid < 52) reinterpret_cast<unsigned short*>(sWh)[(tid - 26) * 40 + 26] = cv;
  const int il = lane & 7, kg = 4 * warp + (lane >> 3);
  const int ilc = min(il, nI - 1);
  const uint32_t colmask = il < nI ? 0xFFF00000u : 0u;
  const uint32_t soff = kg * 128 + (phi < 3 ? 2 * (il & 3) + (il >> 2) : 2 * (il & 3)) * 16;
  uint32_t tab[8];
  mbar_wait(bar + 8, 0);
  if (warp < 11) {
    const uint4 ta = sTab[kg * 2], tb = sTab[kg * 2 + 1];
    tab[0] = ta.x; tab[1] = ta.y; tab[2] = ta.z; tab[3] = ta.w; tab[4] = tb.x; tab[5] = tb.y; tab[6] = tb.z; tab[7] = tb.w;
    if (phi < 3 || il < 4) {
      const unsigned short* w = sW1 + ilc * 676;
      float v[8];
#pragma unroll
      for (int e = 0; e < 8; e++) v[e] = (bf2f(w[tab[e] & 1023]) + bf2f(w[(tab[e] >> 10) & 1023])) * __uint_as_float(tab[e] & colmask);
      *reinterpret_cast<uint4*>(smem + (phi < 3 ? OFF_SX + soff : OFF_SG + soff + 16)) =
          make_uint4(pack_bf16(v[0], v[1]), pack_bf16(v[2], v[3]), pack_bf16(v[4], v[5]), pack_bf16(v[6], v[7]));
    }
  }
  if (warp < 11) {
    const int tc = min(tid, 337);
    float s0 = 0.f, s1 = 0.f, s2 = 0.f, s3 = 0.f;
    float c3[28];
#pragma unroll
    for (int g = 0; g < 28; g += 4) { const float4 c = *reinterpret_cast<const float4*>(sC + 52 + g); c3[g] = c.x; c3[g + 1] = c.y; c3[g + 2] = c.z; c3[g + 3] = c.w; }
    mbar_wait(bar, 0);
    uint32_t v[14];
#pragma unroll
    for (int g = 0; g < 14; g++) v[g] = sW3[g * 338 + tc];
#pragma unroll
    for (int g = 0; g < 14; g += 2) {
      s0 = fmaf(c3[g], __uint_as_float(v[g] << 16), s0); s1 = fmaf(c3[g], __uint_as_float(v[g] & 0xFFFF0000u), s1);
      s2 = fmaf(c3[g + 1], __uint_as_float(v[g + 1] << 16), s2); s3 = fmaf(c3[g + 1], __uint_as_float(v[g + 1] & 0xFFFF0000u), s3);
    }
    mbar_wait(bar + 24, 0);
#pragma unroll
    for (int g = 0; g < 12; g++) v[g] = sW3[(14 + g) * 338 + tc];
#pragma unroll
    for (int g = 0; g < 12; g += 2) {
      s0 = fmaf(c3[14 + g], __uint_as_float(v[g] << 16), s0); s1 = fmaf(c3[14 + g], __uint_as_float(v[g] & 0xFFFF0000u), s1);
      s2 = fmaf(c3[15 + g], __uint_as_float(v[g + 1] << 16), s2); s3 = fmaf(c3[15 + g], __uint_as_float(v[g + 1] & 0xFFFF0000u), s3);
    }
    s0 += s2; s1 += s3;
    if (tid < 338) {
      const int h = (2 * tid) / 26, k = 2 * tid - h * 26;
      sWh[h * 20 + (k >> 1)] = pack_bf16(s0, s1);
    }
  }
  cp_wait<0>();
  named_bar(2, 448);
  if (warp < 13) {
    const int g = lane >> 2, q = lane & 3;
    const int m0 = min(warp * 16 + g, nI * 26 - 1), m1 = min(warp * 16 + g + 8, nI * 26 - 1);
    const uint8_t* e0p = sW2 + 2 * q * 432 + 2 * m0;
    const uint8_t* o0p = sW2 + (2 * q + 1) * 432 + 8 + 2 * m0;
    const uint8_t* e1p = sW2 + 2 * q * 432 + 2 * m1;
    const uint8_t* o1p = sW2 + (2 * q + 1) * 432 + 8 + 2 * m1;
    uint32_t a[2][4];
#pragma unroll
    for (int ks = 0; ks < 2; ks++) {
#pragma unroll
      for (int e = 0; e < 2; e++) {
        const int hb = 16 * ks + 8 * e;
        const bool ok = hb < 24 || q == 0;
        const int o = (ok ? hb : 0) * 432;
        uint32_t x0 = *reinterpret_cast<const unsigned short*>(e0p + o) | ((uint32_t)*reinterpret_cast<const unsigned short*>(o0p + o) << 16);
        uint32_t x1 = *reinterpret_cast<const unsigned short*>(e1p + o) | ((uint32_t)*reinterpret_cast<const unsigned short*>(o1p + o) << 16);
        a[ks][2 * e] = ok ? x0 : 0u; a[ks][2 * e + 1] = ok ? x1 : 0u;
      }
    }
    float d[4][4];
#pragma unroll
    for (int nt = 0; nt < 4; nt++) { d[nt][0] = d[nt][1] = d[nt][2] = d[nt][3] = 0.f; }
    const uint32_t bh = smem_u32(sWh) + (lane & 15) * 80 + (lane >> 4) * 16;
#pragma unroll
    for (int ks = 0; ks < 2; ks++) {
#pragma unroll
      for (int np = 0; np < 2; np++) {
        uint32_t b0, b1, b2, b3;
        ldsm_x4_t(bh + ks * 1280 + np * 32, b0, b1, b2, b3);
        mma_bf16(d[2 * np], a[ks][0], a[ks][1], a[ks][2], a[ks][3], b0, b1);
        mma_bf16(d[2 * np + 1], a[ks][0], a[ks][1], a[ks][2], a[ks][3], b2, b3);
      }
    }
#pragma unroll
    for (int nt = 0; nt < 4; nt++) {
      const int col = 8 * nt + 2 * q, r0 = warp * 16 + g, r1 = r0 + 8;
      if (col < 26) {
        *reinterpret_cast<float2*>(sT + r0 * 26 + col) = make_float2(d[nt][0], d[nt][1]);
        *reinterpret_cast<float2*>(sT + r1 * 26 + col) = make_float2(d[nt][2], d[nt][3]);
      } else if (col == 26) { sA[r0] = d[nt][0]; sA[r1] = d[nt][2]; }
    }
  }
  named_bar(2, 448);
  if (warp < 11) {
    if (phi < 3 || il < 4) {
      const float* t0p = sT + ilc * 676;
      float v[8];
#pragma unroll
      for (int e = 0; e < 8; e++) v[e] = (t0p[tab[e] & 1023] + t0p[(tab[e] >> 10) & 1023]) * __uint_as_float(tab[e] & colmask);
      *reinterpret_cast<uint4*>(smem + OFF_SG + soff) =
          make_uint4(pack_bf16(v[0], v[1]), pack_bf16(v[2], v[3]), pack_bf16(v[4], v[5]), pack_bf16(v[6], v[7]));
    }
  } else if (warp == 11) {
    const int col = lane >> 2, lk = lane & 3;
    const int cil = phi < 3 ? ((col >> 1) | ((col & 1) << 2)) : (col >> 1);
    const bool cok = phi < 3 || ((col & 1) == 0 && cil < 2);
    float v[8];
#pragma unroll
    for (int e = 0; e < 8; e++) {
      const int f = sLin[lk * 8 + e];
      float val = (f != 0xFF) ? sA[min(cil, nI - 1) * 26 + f] : 0.f;
      if (lk == 3 && e == 6) val = sC[i0 + min(cil, nI - 1)];
      v[e] = cok ? val : 0.f;
    }
    *reinterpret_cast<uint4*>(smem + OFF_SL + lk * 128 + col * 16) =
        make_uint4(pack_bf16(v[0], v[1]), pack_bf16(v[2], v[3]), pack_bf16(v[4], v[5]), pack_bf16(v[6], v[7]));
  }
  fence_async_smem();
  named_bar(2, 448);
  if (warp == 0) {
    if (lane == 0) {
      uint8_t* img = reinterpret_cast<uint8_t*>(g_wimg);
      bulk_s2g(img + phi * 512, sb + OFF_SL, 512);
      bulk_s2g(img + CW_P0 + phi * CW_GB0, sb + OFF_SG, CW_GB0);
      bulk_s2g(img + CW_P1 + phi * CW_GB1, sb + OFF_SG + CW_C1 * 256, CW_GB1);
      bulk_s2g(img + CW_P2 + phi * CW_GB2, sb + OFF_SG + CW_C2 * 256, CW_GB2);
      if (phi < 3) {
        bulk_s2g(img + CW_P0 + (4 + phi) * CW_GB0, sb + OFF_SX, CW_GB0);
        bulk_s2g(img + CW_P1 + (4 + phi) * CW_GB1, sb + OFF_SX + CW_C1 * 256, CW_GB1);
        bulk_s2g(img + CW_P2 + (4 + phi) * CW_GB2, sb + OFF_SX + CW_C2 * 256, CW_GB2);
      }
      asm volatile("cp.async.bulk.commit_group;" ::: "memory");
      asm volatile("cp.async.bulk.wait_group 0;" ::: "memory");
    }
    __syncwarp();
    if (lane < kFlagRep) asm volatile("st.relaxed.gpu.global.u8 [%0], %1;" ::"l"(reinterpret_cast<unsigned char*>(&g_flag[(kFlagRep + lane) * 32]) + phi), "r"(1u) : "memory");
  }
}

__global__ void __launch_bounds__(kThreads, 1)
xdeepfm_kernel(const __grid_constant__ CUtensorMap w1map, const __grid_constant__ CUtensorMap w1map2,
               const int* __restrict__ idx, const __nv_bfloat16* __restrict__ table,
               const __nv_bfloat16* __restrict__ ws, const __nv_bfloat16* __restrict__ cout, const __nv_bfloat16* __restrict__ w1,
               const __nv_bfloat16* __restrict__ b1, const __nv_bfloat16* __restrict__ w2, const __nv_bfloat16* __restrict__ bout,
               __nv_bfloat16* __restrict__ out) {
  extern __shared__ uint8_t smem_raw[];
  uint8_t* smem = smem_raw + ((1024u - (smem_u32(smem_raw) & 1023u)) & 1023u);
  const int tid = threadIdx.x, warp = __shfl_sync(0xffffffffu, tid >> 5, 0), lane = tid & 31;
  if (blockIdx.x < kFoldCtas) { fold_cta(smem, ws, cout, w1); return; }

  const unsigned tstart = clk32x();
  const uint32_t sb = smem_u32(smem);
  const int cta = blockIdx.x - kFoldCtas;
  const uint32_t rank = cta & 1;
  const int sample0 = cta * 32;
  const uint32_t bar_l = sb + OFF_BAR, bar_r = bar_l + 56, bar_w1 = bar_l + 112, bar_ovl = bar_l + 144, bar_cw = bar_l + 152, bar_dnn = bar_l + 160,
                 bar_rem = bar_l + 176, bar_bw = bar_l + 184, bar_cw2 = bar_l + 192, bar_cw3 = bar_l + 200;

  if (warp >= 12) {
    asm volatile("setmaxnreg.dec.sync.aligned.u32 32;");
    if (warp == 12) {
      if (lane == 0) {
        asm volatile("prefetch.tensormap [%0];" ::"l"(&w1map) : "memory");
        asm volatile("prefetch.tensormap [%0];" ::"l"(&w1map2) : "memory");
        for (int g = 0; g < 4; g++) mbar_init(bar_w1 + 8 * g, 1);
        asm volatile("fence.mbarrier_init.release.cluster;" ::: "memory");
        for (int c = 0; c < 2; c++) {
          mbar_expect_tx(bar_w1 + 8 * c, W1_CHUNK);
          tma3d(sb + OFF_WA + c * W1_CHUNK, &w1map, 0, 128 * c, 3 * rank, bar_w1 + 8 * c);
        }
      }
      __syncwarp();
      asm volatile("barrier.cluster.arrive.relaxed.aligned;" ::: "memory");
      asm volatile("barrier.cluster.wait.acquire.aligned;" ::: "memory");
      if (lane == 0) {
        while (clk32x() - tstart < kLateW1Clks) { }
        mbar_expect_tx(bar_w1 + 16, W1_CHUNK);
        tma3d(sb + OFF_WA + 2 * W1_CHUNK, &w1map, 0, 256, 3 * rank, bar_w1 + 16);
        mbar_expect_tx(bar_w1 + 24, 12288);
        tma3d(sb + OFF_WD, &w1map2, 0, 384, 3 * rank, bar_w1 + 24);
      }
      __syncwarp();
      forward_rounds(sb, rank, 2, 3, bar_l, bar_r);
    } else if (warp == 13) {
      if (lane == 0) {
        for (int r = 0; r < 7; r++) { mbar_init(bar_l + 8 * r, 8); mbar_init(bar_r + 8 * r, 1); }
        mbar_init(bar_ovl, 4);
        mbar_init(bar_cw, 1);
        mbar_init(bar_cw2, 1);
        mbar_init(bar_cw3, 1);
        mbar_init(bar_dnn, 3);
        mbar_init(bar_rem, 1);
        mbar_init(bar_bw, 1);
        asm volatile("fence.mbarrier_init.release.cluster;" ::: "memory");
        for (int r = 0; r < 7; r++) mbar_expect_tx(bar_r + 8 * r, r < 6 ? 4096 : 2048);
        mbar_expect_tx(bar_dnn, 32 * 4);
      }
      __syncwarp();
      asm volatile("barrier.cluster.arrive.relaxed.aligned;" ::: "memory");
      asm volatile("barrier.cluster.wait.acquire.aligned;" ::: "memory");
      forward_rounds(sb, rank, 0, 3, bar_l, bar_r);
    } else if (warp == 14) {
      asm volatile("barrier.cluster.arrive.relaxed.aligned;" ::: "memory");
      asm volatile("barrier.cluster.wait.acquire.aligned;" ::: "memory");
      if (lane == 0) {
        wait_flags(&g_flag[(cta & (kFlagRep - 1)) * 32]);
        mbar_expect_tx(bar_rem, WR_BYTES);
        bulk_g2s(sb + OFF_W1R, reinterpret_cast<const uint8_t*>(g_rimg) + rank * WR_BYTES, WR_BYTES, bar_rem);
        wait_flags(&g_flag[(kFlagRep + (cta & (kFlagRep - 1))) * 32]);
        mbar_wait(bar_ovl, 0);
        mbar_expect_tx(bar_cw, CW_P1);
        bulk_g2s(sb + OFF_CW, g_wimg, CW_P1, bar_cw);
        mbar_expect_tx(bar_cw2, CW_P2 - CW_P1);
        bulk_g2s(sb + OFF_CW + CW_P1, reinterpret_cast<const uint8_t*>(g_wimg) + CW_P1, CW_P2 - CW_P1, bar_cw2);
        mbar_expect_tx(bar_cw3, CW_BYTES - CW_P2);
        bulk_g2s(sb + OFF_CW + CW_P2, reinterpret_cast<const uint8_t*>(g_wimg) + CW_P2, CW_BYTES - CW_P2, bar_cw3);
        if (atomicAdd(&g_seen, 1) == kMainCtas - 1) { g_seen = 0; for (int r = 0; r < 2 * kFlagRep; r++) g_flag[r * 32] = 0; }
      }
    } else {
      asm volatile("barrier.cluster.arrive.relaxed.aligned;" ::: "memory");
      const unsigned short bov = __bfloat16_as_ushort(bout[0]);
      uint32_t ldv[4];
#pragma unroll
      for (int r = 0; r < 4; r++) ldv[r] = (r * 32 + lane < 112) ? reinterpret_cast<const uint32_t*>(kLdsmOff)[r * 32 + lane] : 0u;
      uint32_t bb[4], ww[4];
#pragma unroll
      for (int r = 0; r < 4; r++) {
        const int u = r * 32 + lane, g = u >> 2, q = u & 3;
        const int n = (g < 24 ? 192 * rank + 8 * g : 384 + 16 * rank + 8 * (g - 24)) + 2 * q;
        bb[r] = u < 104 ? *reinterpret_cast<const uint32_t*>(b1 + n) : 0u;
        ww[r] = u < 104 ? *reinterpret_cast<const uint32_t*>(w2 + n) : 0u;
      }
#pragma unroll
      for (int r = 0; r < 4; r++) {
        const int u = r * 32 + lane;
        if (u < 104) *reinterpret_cast<float4*>(smem + OFF_BW + u * 16) =
            make_float4(__uint_as_float(bb[r] << 16), __uint_as_float(bb[r] & 0xFFFF0000u), 0.5f * __uint_as_float(ww[r] << 16), 0.5f * __uint_as_float(ww[r] & 0xFFFF0000u));
      }
#pragma unroll
      for (int r = 0; r < 4; r++) if (r * 32 + lane < 112) reinterpret_cast<uint32_t*>(smem + OFF_LD)[r * 32 + lane] = ldv[r];
      if (lane == 0) *reinterpret_cast<float*>(smem + OFF_BAR + 240) = bf2f(bov);
      asm volatile("barrier.cluster.wait.acquire.aligned;" ::: "memory");
      __syncwarp();
      if (lane == 0) mbar_arrive(bar_bw);
      forward_rounds(sb, rank, 1, 3, bar_l, bar_r);
    }
  } else if (warp < 4) {
    asm volatile("setmaxnreg.inc.sync.aligned.u32 144;");
    asm volatile("barrier.cluster.arrive.relaxed.aligned;" ::: "memory");
    asm volatile("barrier.cluster.wait.acquire.aligned;" ::: "memory");
    mbar_wait(bar_bw, 0);
    const int q = lane & 3;
    const float4* bwp = reinterpret_cast<const float4*>(smem + OFF_BW) + q;
    float acc1[96], acc2[8];
#pragma unroll
    for (int g = 0; g < 24; g++) { const float2 p = *reinterpret_cast<const float2*>(bwp + g * 4); acc1[4 * g] = acc1[4 * g + 2] = p.x; acc1[4 * g + 1] = acc1[4 * g + 3] = p.y; }
#pragma unroll
    for (int g = 0; g < 2; g++) { const float2 p = *reinterpret_cast<const float2*>(bwp + (24 + g) * 4); acc2[4 * g] = acc2[4 * g + 2] = p.x; acc2[4 * g + 1] = acc2[4 * g + 3] = p.y; }
    const uint32_t wb = (sb & 0x3FFFFu) >> 4;
    const uint32_t xa = (wb + (OFF_X >> 4)) | (1u << 16);
    constexpr uint32_t HI_A = (256 >> 4) | (3u << 30), HI_B = (1024 >> 4) | (1u << 30);
    const uint32_t aL = xa + rank * (XF >> 4), aR = xa + (rank ^ 1) * (XF >> 4);
    const uint32_t bL = wb + rank * 128u, bR = wb + (rank ^ 1) * 128u;
#define W1_BASE(FB) ((FB) < 24 ? OFF_WA + ((FB) >> 3) * W1_CHUNK + ((FB) & 7) * 2048 : OFF_WD + ((FB) - 24) * 2048)
#define W1_AS(FB) (((FB) == 24) ? 4096 : 16384)
#define DNN_A(FB, P) { wgmma_n192_ss(acc1, mk64(a##P + (FB) * (XF >> 4), HI_A), mk64(b##P + ((W1_BASE(FB) >> 4) | ((W1_AS(FB) >> 4) << 16)), HI_B), 1); }
#define DNN_GROUP(BAR, R, P)                                                     \
    {                                                                             \
      mbar_wait((BAR) + 8 * (R), 0);                                              \
      if ((BAR) == bar_l) fence_async_smem();                                     \
      wg_fence();                                                                 \
      DNN_A(4 * (R), P)                                                           \
      if ((R) < 6) DNN_A(((R) < 6 ? 4 * (R) + 2 : 0), P)                          \
    }
    mbar_wait(bar_w1, 0);
    DNN_GROUP(bar_l, 0, L)
    DNN_GROUP(bar_l, 1, L)
    mbar_wait(bar_w1 + 8, 0);
    DNN_GROUP(bar_l, 2, L)
    DNN_GROUP(bar_r, 0, R)
    DNN_GROUP(bar_r, 1, R)
    wg_commit();
    DNN_GROUP(bar_l, 3, L)
    DNN_GROUP(bar_r, 2, R)
    wg_commit();
    wg_wait<1>();
    mbar_arrive_if(bar_ovl, lane == 0);
    mbar_wait(bar_w1 + 16, 0);
    DNN_GROUP(bar_l, 4, L)
    DNN_GROUP(bar_r, 3, R)
    DNN_GROUP(bar_l, 5, L)
    DNN_GROUP(bar_r, 4, R)
    mbar_wait(bar_w1 + 24, 0);
    DNN_GROUP(bar_l, 6, L)
    DNN_GROUP(bar_r, 5, R)
    DNN_GROUP(bar_r, 6, R)
    wg_commit();
    mbar_wait(bar_rem, 0);
    wg_fence();
#pragma unroll
    for (int f = 0; f < 26; f++)
      wgmma_n16_ss(acc2, mk64(xa + f * (XF >> 4), HI_A), mk64(wb + ((OFF_W1R + (f >> 2) * 2048 + (f & 3) * 32) >> 4) + (64u << 16), HI_B), 1);
    wg_commit();
    wg_wait<1>();
    float s0 = 0.f, s1 = 0.f, s2 = 0.f, s3 = 0.f;
    constexpr float K0 = 0.7978845608028654f, K1 = 0.7978845608028654f * 0.044715f;
#define GELU_ACC(S, H, WV) { const float h = (H); const float t = tanh_fast(h * fmaf(h * h, K1, K0)); S = fmaf(fmaf(h, t, h), (WV), S); }
#pragma unroll
    for (int g = 0; g < 24; g++) {
      const float2 p = *(reinterpret_cast<const float2*>(bwp + g * 4) + 1);
      GELU_ACC(s0, acc1[4 * g], p.x) GELU_ACC(s2, acc1[4 * g + 1], p.y)
      GELU_ACC(s1, acc1[4 * g + 2], p.x) GELU_ACC(s3, acc1[4 * g + 3], p.y)
    }
    wg_wait<0>();
#pragma unroll
    for (int g = 0; g < 2; g++) {
      const float2 p = *(reinterpret_cast<const float2*>(bwp + (24 + g) * 4) + 1);
      GELU_ACC(s0, acc2[4 * g], p.x) GELU_ACC(s2, acc2[4 * g + 1], p.y)
      GELU_ACC(s1, acc2[4 * g + 2], p.x) GELU_ACC(s3, acc2[4 * g + 3], p.y)
    }
    s0 += s2; s1 += s3;
    s0 += __shfl_xor_sync(0xffffffffu, s0, 1); s0 += __shfl_xor_sync(0xffffffffu, s0, 2);
    s1 += __shfl_xor_sync(0xffffffffu, s1, 1); s1 += __shfl_xor_sync(0xffffffffu, s1, 2);
    const uint32_t owner = warp >> 1;
    const int li = (warp & 1) * 16 + (lane >> 2);
    const uint32_t dp = sb + OFF_DP + rank * 128 + li * 4;
    if (owner == rank) {
      if (q == 0) { *reinterpret_cast<float*>(smem + OFF_DP + rank * 128 + li * 4) = s0; *reinterpret_cast<float*>(smem + OFF_DP + rank * 128 + li * 4 + 32) = s1; }
      __syncwarp();
      if (lane == 0) mbar_arrive(bar_dnn);
    } else if (q == 0) {
      const uint32_t rdp = mapa(dp, owner), rb = mapa(bar_dnn, owner);
      st_async_f32(rdp, s0, rb); st_async_f32(rdp + 32, s1, rb);
    }
  } else {
    const int gw = warp - 4;
    const int gfs = gw >> 2, gs = 16 * (gw & 3) + (lane >> 1), gh = lane & 1;
    int iv[7];
    {
      const int p = gw & 3, t64 = gfs * 32 + lane;
      const int* ip = idx + ((cta & ~1) * 32 + 16 * p) * kF + t64;
      int* stg = reinterpret_cast<int*>(smem + OFF_X + (2 * p + rank) * XF);
      int v[7];
#pragma unroll
      for (int r = 0; r < 7; r++) v[r] = (r < 6 || t64 < 32) ? __ldg(ip + 64 * r) : 0;
      asm volatile("barrier.cluster.arrive.relaxed.aligned;" ::: "memory");
#pragma unroll
      for (int r = 0; r < 6; r++) stg[64 * r + t64] = v[r];
      if (t64 < 32) stg[384 + t64] = v[6];
      named_bar(5 + p, 64);
      const int* sidx = stg + (lane >> 1) * kF + 2 * gfs + rank;
#pragma unroll
      for (int r = 0; r < 7; r++) iv[r] = (r < 6 || gfs == 0) ? sidx[4 * r] : 0;
    }
    named_bar(2, 256);
    const uint32_t lx = sb + OFF_X + (2 * gfs + rank) * XF + gs * 32;
    const unsigned tpace = clk32x();
#pragma unroll
    for (int r = 0; r < 7; r++) {
      if (r > 0) { while (clk32x() - tpace < r * kPaceClks) { } }
      const uint32_t d0 = lx + r * 4 * XF;
      if (r < 6 || gfs == 0) cp_async16(d0 + ((gh ^ ((d0 >> 7) & 1)) << 4), reinterpret_cast<const char*>(table) + (size_t)iv[r] * 32 + gh * 16);
      cp_commit();
    }
    asm volatile("setmaxnreg.inc.sync.aligned.u32 168;");
    const int wg = (warp >> 2) - 1, w = warp & 3, q = lane & 3;
    asm volatile("barrier.cluster.wait.acquire.aligned;" ::: "memory");
    mbar_wait(bar_bw, 0);
    uint32_t la[7];
#pragma unroll
    for (int t = 0; t < 7; t++) {
      const uint32_t a = sb + OFF_X + reinterpret_cast<const unsigned short*>(smem + OFF_LD)[t * 32 + lane] + (32 * rank + 4 * wg + w) * 32;
      la[t] = a ^ (((a >> 7) & 1) << 4);
    }
#define XROUND(r)                                                                       \
      cp_wait<6 - r>();                                                                  \
      __syncwarp();                                                                      \
      mbar_arrive_if(bar_l + 8 * r, lane == 0);
    XROUND(0) XROUND(1) XROUND(2) XROUND(3) XROUND(4) XROUND(5) XROUND(6)
    const uint32_t selU = q == kMixQ ? 0x3210u : 0x5410u, selV = q == kMixQ ? 0x3210u : 0x7632u;
#pragma unroll
    for (int r = 0; r < 7; r++) { mbar_wait(bar_l + 8 * r, 0); mbar_wait(bar_r + 8 * r, 0); }
    const uint32_t cwl = (((sb & 0x3FFFFu) + OFF_CW) >> 4) | ((128u >> 4) << 16);
    float res[4] = {0.f, 0.f, 0.f, 0.f};
    float base = 0.f;
    uint32_t R[13][2];
    uint32_t toff = 0;
#define L(T, S0, S1) ldsm_x4_t(la[T] + toff, R[S0][0], R[S0][1], R[S1][0], R[S1][1]);
#define LOAD_X() { LDSM_LIST ldsm_x2_t(la[6] + toff, R[LDSM_LAST][0], R[LDSM_LAST][1]); }
    LOAD_X()
    if (wg == 1) asm volatile("bar.arrive 3, 256;" ::: "memory");
#pragma unroll 1
    for (int tile = 0; tile < 4; tile++) {
      constexpr int C1 = CW_C1, C2 = CW_C2;
      uint32_t A[44][2];
#define X(P, TY, S, T)  if ((P) >= PLO && (P) < PHI) {                                            \
      if (TY == 0) { A[P][0] = bmul_lo(R[S][0], R[T][0]); A[P][1] = bmul_lo(R[S][1], R[T][1]); } \
      else if (TY == 1) { A[P][0] = bmul(R[S][0], R[S][0]); A[P][1] = bmul(R[S][1], R[S][1]); }  \
      else if (TY == 2) { A[P][0] = bmul(__byte_perm(R[S][0], R[T][0], 0x5410), __byte_perm(R[S][0], R[T][0], 0x7632)); \
                          A[P][1] = bmul(__byte_perm(R[S][1], R[T][1], 0x5410), __byte_perm(R[S][1], R[T][1], 0x7632)); } \
      else { A[P][0] = bmul(__byte_perm(R[S][0], R[T][0], selU), __byte_perm(R[S][0], R[T][0], selV));                    \
             A[P][1] = bmul(__byte_perm(R[S][1], R[T][1], selU), __byte_perm(R[S][1], R[T][1], selV)); } }
#define CIN_MMA(S0, S1)                                                                                                   \
      _Pragma("unroll") for (int s = (S0); s < (S1); s++) {                                                                \
        wgmma_n56_rs(acc, A[2 * s][0], A[2 * s][1], A[2 * s + 1][0], A[2 * s + 1][1],                                      \
                     mk64(cwl + (s < CW_C1 ? (CW_P0 >> 4) + s * 16 : s < CW_C2 ? (CW_P1 >> 4) + (s - CW_C1) * 16 : (CW_P2 >> 4) + (s - CW_C2) * 16), \
                          (s < CW_C1 ? CW_GB0 : s < CW_C2 ? CW_GB1 : CW_GB2) >> 4), s > 0);                                \
        if (s == kHandOver && (wg == 0 || tile < 3)) asm volatile("bar.arrive %0, 256;" ::"r"(4 - wg) : "memory");          \
      }
      { constexpr int PLO = 0, PHI = 2 * C1; PROD_LIST }
      const uint32_t l0 = q == 3 ? 0x00003F80u : R[kLin3][0], l1 = q == 3 ? 0x00003F80u : R[kLin3][1];
      if (tile == 0) mbar_wait(bar_cw, 0);
      float acc[28], accL[16];
      named_bar(3 + wg, 256);
      wg_fence();
      wgmma_n32_rs(accL, R[kLin0][0], R[kLin0][1], R[kLin1][0], R[kLin1][1], mk64(cwl, 512 >> 4), 0);
      wgmma_n32_rs(accL, R[kLin2][0], R[kLin2][1], l0, l1, mk64(cwl + 16, 512 >> 4), 1);
      CIN_MMA(0, C1)
      wg_commit();
      { constexpr int PLO = 2 * C1, PHI = 2 * C2; PROD_LIST }
      if (tile == 0) mbar_wait(bar_cw2, 0);
      wg_fence();
      CIN_MMA(C1, C2)
      wg_commit();
      wg_wait<1>();
      { constexpr int PLO = 2 * C2, PHI = 44; PROD_LIST }
      if (tile == 0) mbar_wait(bar_cw3, 0);
      wg_fence();
      CIN_MMA(C2, 22)
#undef X
      wg_commit();
      if (tile == 3) {
        mbar_wait_cluster(bar_dnn, 0);
        const int li = 8 * (lane & 3) + 4 * wg + w;
        const float* dp = reinterpret_cast<const float*>(smem + OFF_DP);
        base = dp[li] + dp[32 + li] + *reinterpret_cast<const float*>(smem + OFF_BAR + 240);
      }
      wg_wait<0>();
      toff = (tile + 1) * 256;
      LOAD_X()
      float r0 = 0.f, r1 = 0.f, r2 = 0.f, r3 = 0.f;
#pragma unroll
      for (int j = 0; j < 7; j++) {
        const int gi = 4 * (j >> 1) + (j & 1);
        const int xi = j == 6 ? 13 : 4 * (4 + (j >> 1)) + (j & 1);
        if (j & 1) { r2 = fmaf(acc[gi] + accL[gi], acc[xi], r2); r3 = fmaf(acc[gi + 2] + accL[gi + 2], acc[xi + 2], r3); }
        else       { r0 = fmaf(acc[gi] + accL[gi], acc[xi], r0); r1 = fmaf(acc[gi + 2] + accL[gi + 2], acc[xi + 2], r1); }
      }
      const float rt = (r0 + r1) + (r2 + r3);
      res[0] = tile == 0 ? rt : res[0]; res[1] = tile == 1 ? rt : res[1]; res[2] = tile == 2 ? rt : res[2]; res[3] = rt;
    }
#undef L
    float myres;
    {
      const bool b0 = lane & 1, b1 = lane & 2;
      float u0 = b0 ? res[1] : res[0], v0 = b0 ? res[0] : res[1];
      float u1 = b0 ? res[3] : res[2], v1 = b0 ? res[2] : res[3];
      u0 += __shfl_xor_sync(0xffffffffu, v0, 1);
      u1 += __shfl_xor_sync(0xffffffffu, v1, 1);
      float x = b1 ? u1 : u0, y = b1 ? u0 : u1;
      x += __shfl_xor_sync(0xffffffffu, y, 2);
      x += __shfl_xor_sync(0xffffffffu, x, 4);
      x += __shfl_xor_sync(0xffffffffu, x, 8);
      x += __shfl_xor_sync(0xffffffffu, x, 16);
      myres = x;
    }
    if (lane < 4) out[sample0 + 8 * lane + 4 * wg + w] = __float2bfloat16(myres + base);
  }
}

typedef CUresult (*EncodeFn)(CUtensorMap*, CUtensorMapDataType, cuuint32_t, void*, const cuuint64_t*, const cuuint64_t*, const cuuint32_t*,
                             const cuuint32_t*, CUtensorMapInterleave, CUtensorMapSwizzle, CUtensorMapL2promotion, CUtensorMapFloatOOBfill);
}

extern "C" void kernel_launch(void* const* d_in, const int* in_sizes, int n_in, void* d_out, int out_size) {
  const int* idx = (const int*)d_in[0];
  const __nv_bfloat16* table = (const __nv_bfloat16*)d_in[1];
  const __nv_bfloat16* ws = (const __nv_bfloat16*)d_in[2];
  const __nv_bfloat16* cout = (const __nv_bfloat16*)d_in[3];
  const __nv_bfloat16* w1 = (const __nv_bfloat16*)d_in[4];
  const __nv_bfloat16* b1 = (const __nv_bfloat16*)d_in[5];
  const __nv_bfloat16* w2 = (const __nv_bfloat16*)d_in[6];
  const __nv_bfloat16* bout = (const __nv_bfloat16*)d_in[7];
  static EncodeFn enc = nullptr;
  if (!enc) {
    void* fn = nullptr; cudaDriverEntryPointQueryResult qr;
    cudaGetDriverEntryPoint("cuTensorMapEncodeTiled", &fn, cudaEnableDefault, &qr);
    enc = (EncodeFn)fn;
    cudaFuncSetAttribute(xdeepfm_kernel, cudaFuncAttributeMaxDynamicSharedMemorySize, SMEM_ALLOC);
  }
  CUtensorMap m, m2;
  const cuuint32_t es[3] = {1, 1, 1};
  {
    cuuint64_t dims[3] = {64, 416, 6};
    cuuint64_t strides[2] = {832, 128};
    cuuint32_t box[3] = {64, 128, 3}, box2[3] = {64, 32, 3};
    enc(&m, CU_TENSOR_MAP_DATA_TYPE_BFLOAT16, 3, (void*)w1, dims, strides, box, es, CU_TENSOR_MAP_INTERLEAVE_NONE,
        CU_TENSOR_MAP_SWIZZLE_128B, CU_TENSOR_MAP_L2_PROMOTION_L2_128B, CU_TENSOR_MAP_FLOAT_OOB_FILL_NONE);
    enc(&m2, CU_TENSOR_MAP_DATA_TYPE_BFLOAT16, 3, (void*)w1, dims, strides, box2, es, CU_TENSOR_MAP_INTERLEAVE_NONE,
        CU_TENSOR_MAP_SWIZZLE_128B, CU_TENSOR_MAP_L2_PROMOTION_L2_128B, CU_TENSOR_MAP_FLOAT_OOB_FILL_NONE);
  }
  cudaLaunchConfig_t cfg = {};
  cfg.gridDim = dim3(kFoldCtas + kMainCtas);
  cfg.blockDim = dim3(kThreads);
  cfg.dynamicSmemBytes = SMEM_ALLOC;
  cfg.stream = cudaStreamPerThread;
  cudaLaunchAttribute at[1];
  at[0].id = cudaLaunchAttributeClusterDimension;
  at[0].val.clusterDim.x = 2; at[0].val.clusterDim.y = 1; at[0].val.clusterDim.z = 1;
  cfg.attrs = at; cfg.numAttrs = 1;
  cudaLaunchKernelEx(&cfg, xdeepfm_kernel, m, m2, idx, table, ws, cout, w1, b1, w2, bout, (__nv_bfloat16*)d_out);
}
```
